```python
import torch

def _softmax(x, axis=-1):
    return torch.softmax(x, dim=axis)
def _gelu(x):
    return torch.nn.functional.gelu(x, approximate="tanh")
def _silu(x):
    return torch.nn.functional.silu(x)
def _sigmoid(x):
    return torch.sigmoid(x)
def _layernorm(x, axis=-1, eps=1e-5):
    m = x.mean(dim=axis, keepdim=True)
    v = x.var(dim=axis, keepdim=True, unbiased=False)
    return (x - m) / torch.sqrt(v + eps)
def _scatter_add(tgt, idx, src, axis=0):
    return tgt.clone().index_add_(axis, idx, src)
def _segment_sum(src, seg, n):
    out = torch.zeros((n,) + src.shape[1:], dtype=src.dtype)
    return out.index_add_(0, seg, src)
def _pad(x, pw):
    flat = tuple(v for pair in reversed(pw) for v in pair)
    return torch.nn.functional.pad(x, flat)

kernel_name = 'parallel_sum__mha_block_cached__dense_activation_silu__decode'

def setup_inputs():

    _w = (lambda a: (lambda t: t.to(torch.bfloat16) if t.is_floating_point() else t)(torch.as_tensor(a)))
    def _A_setup():
        B, Sq, D = 8, 1, 448
        H, Sk, Dh = 16, 4096, 256
        return {
            "x": _w((lambda *s: torch.randn(*s, dtype=torch.bfloat16) * 0.05)(B, Sq, D)),
            "k_cache": _w((lambda *s: torch.randn(*s, dtype=torch.bfloat16) * 3.2)(B, H, Sk, Dh)),
            "v_cache": _w((lambda *s: torch.randn(*s, dtype=torch.bfloat16) * 0.8)(B, H, Sk, Dh)),
            "wq": _w((lambda *s: torch.randn(*s, dtype=torch.bfloat16) * 3.2)(D, H * Dh) * (D ** -0.5)),
            "wo": _w((lambda *s: torch.randn(*s, dtype=torch.bfloat16) * 0.8)(H * Dh, D) * ((H * Dh) ** -0.5)),
        }
    _A_in = _A_setup()

    def _B_setup():
        B, S, D, F = 8, 1, 448, 1792
        return {
            "x": _w((lambda *s: torch.randn(*s, dtype=torch.bfloat16) * 0.05)(B, S, D)),
            "w1": _w((lambda *s: torch.randn(*s, dtype=torch.bfloat16) * 3.2)(D, F) * (D ** -0.5)),
            "w2": _w((lambda *s: torch.randn(*s, dtype=torch.bfloat16) * 0.4)(F, D) * (F ** -0.5)),
        }
    _B_in = _B_setup()

    return {
        "A_x": _A_in["x"],
        "A_k_cache": _A_in["k_cache"],
        "A_v_cache": _A_in["v_cache"],
        "A_wq": _A_in["wq"],
        "A_wo": _A_in["wo"],
        "B_x": _B_in["x"],
        "B_w1": _B_in["w1"],
        "B_w2": _B_in["w2"],
    }

def reference(A_x, A_k_cache, A_v_cache, A_wq, A_wo, B_x, B_w1, B_w2):
    def _A_ref(x, k_cache, v_cache, wq, wo):
        B, Sq, D = x.shape
        H, Dh = 16, 256
        q = (lambda x, *d: x.permute(*d))((x @ wq).reshape(B, Sq, H, Dh), 0, 2, 1, 3)
        scores = torch.einsum("bhqd,bhkd->bhqk", q, k_cache) * (Dh ** -0.5)
        p = _softmax(scores, axis=-1)
        o = torch.einsum("bhqk,bhkd->bhqd", p, v_cache)
        return (lambda x, *d: x.permute(*d))(o, 0, 2, 1, 3).reshape(B, Sq, H * Dh) @ wo

    def _B_ref(x, w1, w2):
        h = torch.einsum("bsd,df->bsf", x, w1)
        h = _silu(h)
        out = torch.einsum("bsf,fd->bsd", h, w2)
        return out

    x = A_x
    xn = _layernorm(x, axis=-1)
    return x + _A_ref(xn, A_k_cache, A_v_cache, A_wq, A_wo) + _B_ref(xn, B_w1, B_w2)
```

```cpp
#include <cuda_runtime.h>
#include <cuda_bf16.h>
#include <stdint.h>

namespace {

constexpr int D_ = 448, SK = 4096, DH = 256, F_ = 1792;
constexpr int NATT = 128, NFFN = 4;
constexpr int NCW = 8;
constexpr int NTHREADS = (NCW + 1) * 32;
constexpr int STAGE = 16384;
constexpr int NS = 12;
constexpr int NPAIR = SK / 32;
constexpr int WO_TILE = 16 * 896;
constexpr int NSRC = 16 + NFFN;
constexpr int FP = 912;

constexpr int SM_RING = 0;
constexpr int SM_A = NS * STAGE;
constexpr int SM_Q = SM_A + 14592;
constexpr int SM_ML = SM_Q + 512;
constexpr int SM_BAR = SM_ML + 64;
constexpr int SMEM_BYTES = SM_BAR + 2 * NS * 8;

constexpr int THR_WINDOW = 128;
constexpr int THR_FREE = 2;

__device__ uint32_t g_q[NATT * 128];
__device__ uint32_t g_part[8 * NSRC * D_];
__device__ uint32_t g_prog;

__device__ __forceinline__ uint32_t smem_u32(const void* p) { return (uint32_t)__cvta_generic_to_shared(p); }
__device__ __forceinline__ void mbar_init(uint32_t bar, int cnt) {
    asm volatile("mbarrier.init.shared::cta.b64 [%0], %1;" ::"r"(bar), "r"(cnt) : "memory");
}
__device__ __forceinline__ void mbar_expect_tx(uint32_t bar, uint32_t bytes) {
    asm volatile("mbarrier.arrive.expect_tx.shared::cta.b64 _, [%0], %1;" ::"r"(bar), "r"(bytes) : "memory");
}
__device__ __forceinline__ void mbar_arrive(uint32_t bar) {
    asm volatile("mbarrier.arrive.shared::cta.b64 _, [%0];" ::"r"(bar) : "memory");
}
__device__ __forceinline__ bool mbar_try_wait(uint32_t bar, uint32_t parity) {
    uint32_t ok;
    asm volatile(
        "{\n.reg .pred p;\nmbarrier.try_wait.parity.shared::cta.b64 p, [%1], %2;\nselp.u32 %0, 1, 0, p;\n}"
        : "=r"(ok) : "r"(bar), "r"(parity) : "memory");
    return ok;
}
__device__ __forceinline__ void mbar_wait(uint32_t bar, uint32_t parity) {
    int it = 0;
    while (!mbar_try_wait(bar, parity)) {
        if (++it > (1 << 22)) __trap();
    }
}
__device__ __forceinline__ void bulk_load(uint32_t dst, const void* src, uint32_t bytes, uint32_t bar) {
    asm volatile("cp.async.bulk.shared::cluster.global.mbarrier::complete_tx::bytes [%0], [%1], %2, [%3];"
                 ::"r"(dst), "l"(src), "r"(bytes), "r"(bar) : "memory");
}
__device__ __forceinline__ void ldsm4(uint32_t (&r)[4], uint32_t addr) {
    asm volatile("ldmatrix.sync.aligned.m8n8.x4.shared.b16 {%0,%1,%2,%3}, [%4];"
                 : "=r"(r[0]), "=r"(r[1]), "=r"(r[2]), "=r"(r[3]) : "r"(addr) : "memory");
}
__device__ __forceinline__ void ldsm4t(uint32_t (&r)[4], uint32_t addr) {
    asm volatile("ldmatrix.sync.aligned.m8n8.x4.trans.shared.b16 {%0,%1,%2,%3}, [%4];"
                 : "=r"(r[0]), "=r"(r[1]), "=r"(r[2]), "=r"(r[3]) : "r"(addr) : "memory");
}
__device__ __forceinline__ void mma16816(float (&c)[4], const uint32_t (&a)[4], uint32_t b0, uint32_t b1) {
    asm volatile(
        "mma.sync.aligned.m16n8k16.row.col.f32.bf16.bf16.f32 {%0,%1,%2,%3}, {%4,%5,%6,%7}, {%8,%9}, {%0,%1,%2,%3};"
        : "+f"(c[0]), "+f"(c[1]), "+f"(c[2]), "+f"(c[3])
        : "r"(a[0]), "r"(a[1]), "r"(a[2]), "r"(a[3]), "r"(b0), "r"(b1));
}
__device__ __forceinline__ void bar_cons() { asm volatile("bar.sync 1, 256;" ::: "memory"); }
__device__ __forceinline__ float bf16r(float x) { return __bfloat162float(__float2bfloat16_rn(x)); }
__device__ __forceinline__ uint32_t bf16bits(float x) { return (uint32_t)__bfloat16_as_ushort(__float2bfloat16_rn(x)); }
__device__ __forceinline__ float bflo(uint32_t w) { return __uint_as_float(w << 16); }
__device__ __forceinline__ float bfhi(uint32_t w) { return __uint_as_float(w & 0xffff0000u); }
__device__ __forceinline__ float ex2(float x) { float y; asm("ex2.approx.ftz.f32 %0, %1;" : "=f"(y) : "f"(x)); return y; }
__device__ __forceinline__ uint32_t ld_relaxed(const uint32_t* p) {
    uint32_t v; asm volatile("ld.relaxed.gpu.global.u32 %0, [%1];" : "=r"(v) : "l"(p) : "memory"); return v;
}
__device__ __forceinline__ uint4 ld_relaxed4(const uint32_t* p) {
    uint4 v;
    asm volatile("ld.relaxed.gpu.global.v4.u32 {%0,%1,%2,%3}, [%4];" : "=r"(v.x), "=r"(v.y), "=r"(v.z), "=r"(v.w) : "l"(p) : "memory");
    return v;
}
__device__ __forceinline__ void st_relaxed(uint32_t* p, uint32_t v) {
    asm volatile("st.relaxed.gpu.global.u32 [%0], %1;" ::"l"(p), "r"(v) : "memory");
}
__device__ __forceinline__ void st_relaxed4(uint32_t* p, uint4 v) {
    asm volatile("st.relaxed.gpu.global.v4.u32 [%0], {%1,%2,%3,%4};" ::"l"(p), "r"(v.x), "r"(v.y), "r"(v.z), "r"(v.w) : "memory");
}
__device__ __forceinline__ uint32_t enc_f32(float v) { return __float_as_uint(v + 0.0f) ^ 0x80000000u; }
__device__ __forceinline__ float dec_f32(uint32_t w) { return __uint_as_float(w ^ 0x80000000u); }
__device__ __forceinline__ bool all_set(const uint4& v) { return v.x != 0u && v.y != 0u && v.z != 0u && v.w != 0u; }

__device__ __forceinline__ void layernorm_row(const __nv_bfloat16* __restrict__ x, int row, int lane, float (&xn)[14]) {
    const uint32_t* xr = reinterpret_cast<const uint32_t*>(x + row * D_);
    float v[14];
#pragma unroll
    for (int i = 0; i < 7; i++) {
        uint32_t w = __ldg(xr + lane + 32 * i);
        v[2 * i] = bflo(w); v[2 * i + 1] = bfhi(w);
    }
    float s = 0.f;
#pragma unroll
    for (int i = 0; i < 14; i++) s += v[i];
#pragma unroll
    for (int o = 16; o > 0; o >>= 1) s += __shfl_xor_sync(0xffffffffu, s, o);
    const float mean = s * (1.0f / D_);
    float ss = 0.f;
#pragma unroll
    for (int i = 0; i < 14; i++) { float d = v[i] - mean; ss += d * d; }
#pragma unroll
    for (int o = 16; o > 0; o >>= 1) ss += __shfl_xor_sync(0xffffffffu, ss, o);
    const float mb = bf16r(mean);
    const float var = bf16r(ss * (1.0f / D_));
    const float den = bf16r(sqrtf(bf16r(var + 1e-5f)));
#pragma unroll
    for (int i = 0; i < 14; i++) xn[i] = bf16r(__fdiv_rn(bf16r(v[i] - mb), den));
}

__global__ void __launch_bounds__(NTHREADS, 1)
fused_decode_kernel(const __nv_bfloat16* __restrict__ x, const __nv_bfloat16* __restrict__ kc,
                    const __nv_bfloat16* __restrict__ vc, const __nv_bfloat16* __restrict__ wq,
                    const __nv_bfloat16* __restrict__ wo, const __nv_bfloat16* __restrict__ w1,
                    const __nv_bfloat16* __restrict__ w2, __nv_bfloat16* __restrict__ out) {
    extern __shared__ __align__(1024) unsigned char smem[];
    const uint32_t sb = smem_u32(smem);
    const int tid = threadIdx.x, warp = tid >> 5, lane = tid & 31;
    const int cta = blockIdx.x;
    const bool is_att = cta < NATT;
    const uint32_t bar_full = sb + SM_BAR, bar_empty = sb + SM_BAR + NS * 8;

    if (tid == NCW * 32) {
        for (int i = 0; i < NS; i++) {
            mbar_init(bar_full + 8 * i, 1);
            mbar_init(bar_empty + 8 * i, is_att ? 1 : 7);
        }
        asm volatile("fence.mbarrier_init.release.cluster;" ::: "memory");
    }
    __syncthreads();

    const int g = lane >> 2, t = lane & 3;
    const int lr = lane & 7, lm = lane >> 3;

    if (is_att) {
        const int b = cta & 7, h = cta >> 3;
        if (warp == NCW) {
            if (lane == 0) {
                const size_t base = (size_t)(b * 16 + h) * SK * DH * 2;
                const char* kp = reinterpret_cast<const char*>(kc) + base;
                const char* vp = reinterpret_cast<const char*>(vc) + base;
                const char* wp = reinterpret_cast<const char*>(wo) + (size_t)h * DH * D_ * 2;
                int s = 0; uint32_t ph = 1;
                uint32_t G = 0;
                for (int j = 0; j < NPAIR; j++) {
                    mbar_wait(bar_empty + 8 * s, ph);
                    if (j >= THR_FREE) {
                        int it = 0;
                        while ((uint32_t)(j * NATT) > (G & 16383u) + THR_WINDOW) {
                            G = ld_relaxed(&g_prog);
                            if (++it > (1 << 22)) __trap();
                        }
                    }
                    G = atomicAdd(&g_prog, 1u);
                    mbar_expect_tx(bar_full + 8 * s, STAGE);
                    bulk_load(sb + SM_RING + s * STAGE, kp + (size_t)j * STAGE, STAGE, bar_full + 8 * s);
                    if (++s == NS) { s = 0; ph ^= 1; }
                    mbar_wait(bar_empty + 8 * s, ph);
                    mbar_expect_tx(bar_full + 8 * s, STAGE);
                    bulk_load(sb + SM_RING + s * STAGE, vp + (size_t)j * STAGE, STAGE, bar_full + 8 * s);
                    if (++s == NS) { s = 0; ph ^= 1; }
                }
                for (int j = 0; j < 16; j++) {
                    mbar_wait(bar_empty + 8 * s, ph);
                    mbar_expect_tx(bar_full + 8 * s, WO_TILE);
                    bulk_load(sb + SM_RING + s * STAGE, wp + (size_t)j * WO_TILE, WO_TILE, bar_full + 8 * s);
                    if (++s == NS) { s = 0; ph ^= 1; }
                }
            }
            return;
        }
        float* sA = reinterpret_cast<float*>(smem + SM_A);
        {
            const int c4 = tid & 3, rg = tid >> 2;
            uint4 w[7];
#pragma unroll
            for (int i = 0; i < 7; i++)
                w[i] = __ldg(reinterpret_cast<const uint4*>(wq + (size_t)(rg + 64 * i) * 4096 + 32 * cta + 8 * c4));
            float xn[14];
            layernorm_row(x, warp, lane, xn);
#pragma unroll
            for (int i = 0; i < 7; i++) {
                sA[(2 * lane + 64 * i) * 8 + warp] = xn[2 * i];
                sA[(2 * lane + 64 * i + 1) * 8 + warp] = xn[2 * i + 1];
            }
            bar_cons();
            float acc[8][8];
#pragma unroll
            for (int bb = 0; bb < 8; bb++)
#pragma unroll
                for (int j = 0; j < 8; j++) acc[bb][j] = 0.f;
#pragma unroll
            for (int i = 0; i < 7; i++) {
                const float4 xa = *reinterpret_cast<const float4*>(sA + (rg + 64 * i) * 8);
                const float4 xb = *reinterpret_cast<const float4*>(sA + (rg + 64 * i) * 8 + 4);
                const float xv[8] = {xa.x, xa.y, xa.z, xa.w, xb.x, xb.y, xb.z, xb.w};
                const float wv[8] = {bflo(w[i].x), bfhi(w[i].x), bflo(w[i].y), bfhi(w[i].y),
                                     bflo(w[i].z), bfhi(w[i].z), bflo(w[i].w), bfhi(w[i].w)};
#pragma unroll
                for (int bb = 0; bb < 8; bb++)
#pragma unroll
                    for (int j = 0; j < 8; j++) acc[bb][j] = fmaf(xv[bb], wv[j], acc[bb][j]);
            }
            float r4[4][8], r2[2][8], r1[8];
            const bool h4 = lane & 16, h3 = lane & 8, h2 = lane & 4;
#pragma unroll
            for (int bb = 0; bb < 4; bb++)
#pragma unroll
                for (int j = 0; j < 8; j++) {
                    float send = h4 ? acc[bb][j] : acc[bb + 4][j];
                    float keep = h4 ? acc[bb + 4][j] : acc[bb][j];
                    r4[bb][j] = keep + __shfl_xor_sync(0xffffffffu, send, 16);
                }
#pragma unroll
            for (int bb = 0; bb < 2; bb++)
#pragma unroll
                for (int j = 0; j < 8; j++) {
                    float send = h3 ? r4[bb][j] : r4[bb + 2][j];
                    float keep = h3 ? r4[bb + 2][j] : r4[bb][j];
                    r2[bb][j] = keep + __shfl_xor_sync(0xffffffffu, send, 8);
                }
#pragma unroll
            for (int j = 0; j < 8; j++) {
                float send = h2 ? r2[0][j] : r2[1][j];
                float keep = h2 ? r2[1][j] : r2[0][j];
                r1[j] = keep + __shfl_xor_sync(0xffffffffu, send, 4);
            }
            bar_cons();
            float* rp = sA + warp * 256 + (lane >> 2) * 32 + c4 * 8;
            *reinterpret_cast<float4*>(rp) = make_float4(r1[0], r1[1], r1[2], r1[3]);
            *reinterpret_cast<float4*>(rp + 4) = make_float4(r1[4], r1[5], r1[6], r1[7]);
            bar_cons();
            float qv = 0.f;
#pragma unroll
            for (int ww = 0; ww < 8; ww++) qv += sA[ww * 256 + tid];
            uint32_t qb = bf16bits(qv + 0.0f);
            uint32_t other = __shfl_down_sync(0xffffffffu, qb, 1);
            if ((lane & 1) == 0) {
                uint32_t word = (qb | (other << 16)) ^ 0x00008000u;
                st_relaxed(&g_q[(h * 8 + warp) * 128 + b * 16 + (lane >> 1)], word);
            }
            uint32_t* qs = reinterpret_cast<uint32_t*>(smem + SM_Q);
            if (tid < 128) {
                uint32_t* src = &g_q[cta * 128 + tid];
                uint32_t wv = ld_relaxed(src);
                int it = 0;
                while (wv == 0u) {
                    wv = ld_relaxed(src);
                    if (++it > (1 << 22)) __trap();
                }
                st_relaxed(src, 0u);
                qs[tid] = wv ^ 0x00008000u;
            }
            bar_cons();
        }
        uint32_t qf[32];
        {
            const uint32_t* qs = reinterpret_cast<const uint32_t*>(smem + SM_Q);
#pragma unroll
            for (int v = 0; v < 32; v++) qf[v] = qs[((v ^ g) << 2) + t];
        }

        uint32_t koff[4], voff[4];
#pragma unroll
        for (int j = 0; j < 4; j++) {
            koff[j] = ((lm & 1) * 8 + lr) * 512 + (((2 * j + (lm >> 1)) ^ lr) << 4);
            voff[j] = ((lm >> 1) * 8 + lr) * 512 + (((2 * j + (lm & 1)) ^ lr) << 4);
        }
        const bool holder = (t == (g >> 1));
        const bool odd = g & 1;
        constexpr float SCL = 1.4426950408889634f * 0.0625f;

        float o[16][4];
#pragma unroll
        for (int c = 0; c < 16; c++) { o[c][0] = o[c][1] = o[c][2] = o[c][3] = 0.f; }
        float m_run = -INFINITY, l_run = 0.f;

        for (int p = (warp < NS / 2) ? warp : NPAIR; p < NPAIR; p += NS / 2) {
            const int ik = 2 * p;
            const int sk = ik % NS, sv = (ik + 1) % NS;
            const uint32_t phk = (ik / NS) & 1, phv = ((ik + 1) / NS) & 1;
            const uint32_t kb = sb + SM_RING + sk * STAGE, vb = sb + SM_RING + sv * STAGE;
            mbar_wait(bar_full + 8 * sk, phk);
            float sc[4][4];
#pragma unroll
            for (int i = 0; i < 4; i++) { sc[i][0] = sc[i][1] = sc[i][2] = sc[i][3] = 0.f; }
#pragma unroll
            for (int c = 0; c < 16; c++) {
                uint32_t a0[4], a1[4];
                ldsm4(a0, kb + koff[c & 3] + (c >> 2) * 128);
                ldsm4(a1, kb + koff[c & 3] + (c >> 2) * 128 + 8192);
                mma16816(sc[c & 1], a0, qf[2 * c], qf[2 * c + 1]);
                mma16816(sc[2 + (c & 1)], a1, qf[2 * c], qf[2 * c + 1]);
            }
            __syncwarp();
            if (lane == 0) mbar_arrive(bar_empty + 8 * sk);
            float s0 = bf16r(odd ? sc[0][1] + sc[1][1] : sc[0][0] + sc[1][0]);
            float s1 = bf16r(odd ? sc[0][3] + sc[1][3] : sc[0][2] + sc[1][2]);
            float s2 = bf16r(odd ? sc[2][1] + sc[3][1] : sc[2][0] + sc[3][0]);
            float s3 = bf16r(odd ? sc[2][3] + sc[3][3] : sc[2][2] + sc[3][2]);
            float mx = holder ? fmaxf(fmaxf(s0, s1), fmaxf(s2, s3)) : -INFINITY;
#pragma unroll
            for (int of = 16; of > 0; of >>= 1) mx = fmaxf(mx, __shfl_xor_sync(0xffffffffu, mx, of));
            if (mx > m_run) {
                const float sca = ex2((m_run - mx) * SCL);
                m_run = mx;
                l_run *= sca;
#pragma unroll
                for (int c = 0; c < 16; c++) { o[c][0] *= sca; o[c][1] *= sca; o[c][2] *= sca; o[c][3] *= sca; }
            }
            const float ms = (m_run == -INFINITY) ? 0.f : m_run;
            const float p0 = ex2((s0 - ms) * SCL), p1 = ex2((s1 - ms) * SCL);
            const float p2 = ex2((s2 - ms) * SCL), p3 = ex2((s3 - ms) * SCL);
            uint32_t pb0 = 0, pb1 = 0, pb2 = 0, pb3 = 0;
            if (holder) {
                l_run += (p0 + p1) + (p2 + p3);
                const int sh = odd ? 16 : 0;
                pb0 = bf16bits(p0) << sh; pb1 = bf16bits(p1) << sh;
                pb2 = bf16bits(p2) << sh; pb3 = bf16bits(p3) << sh;
            }
            mbar_wait(bar_full + 8 * sv, phv);
#pragma unroll
            for (int c = 0; c < 16; c++) {
                uint32_t a0[4], a1[4];
                ldsm4t(a0, vb + voff[c & 3] + (c >> 2) * 128);
                ldsm4t(a1, vb + voff[c & 3] + (c >> 2) * 128 + 8192);
                mma16816(o[c], a0, pb0, pb1);
                mma16816(o[c], a1, pb2, pb3);
            }
            __syncwarp();
            if (lane == 0) mbar_arrive(bar_empty + 8 * sv);
        }

        {
            float e[16], f[16];
#pragma unroll
            for (int c = 0; c < 16; c++) { e[c] = o[c][0] + o[c][3]; f[c] = o[c][1] + o[c][2]; }
#pragma unroll
            for (int c = 0; c < 16; c += 2) {
                e[c] += __shfl_xor_sync(0xffffffffu, e[c + 1], 1);
                f[c] += __shfl_xor_sync(0xffffffffu, f[c + 1], 1);
            }
#pragma unroll
            for (int c = 0; c < 16; c += 4) {
                e[c] += __shfl_xor_sync(0xffffffffu, e[c + 2], 2);
                f[c] += __shfl_xor_sync(0xffffffffu, f[c + 2], 2);
            }
#pragma unroll
            for (int c = 0; c < 16; c += 4) {
                sA[warp * 256 + (c + t) * 16 + g] = e[c];
                sA[warp * 256 + (c + t) * 16 + 8 + g] = f[c];
            }
#pragma unroll
            for (int of = 16; of > 0; of >>= 1) l_run += __shfl_xor_sync(0xffffffffu, l_run, of);
            float* ml = reinterpret_cast<float*>(smem + SM_ML);
            if (lane == 0) { ml[warp] = m_run; ml[8 + warp] = l_run; }
            bar_cons();
            float M = ml[0];
#pragma unroll
            for (int ww = 1; ww < 8; ww++) M = fmaxf(M, ml[ww]);
            const float Ms = (M == -INFINITY) ? 0.f : M;
            float L = 0.f, ov = 0.f;
#pragma unroll
            for (int ww = 0; ww < 8; ww++) {
                const float sca = ex2((ml[ww] - Ms) * SCL);
                L = fmaf(ml[8 + ww], sca, L);
                ov = fmaf(sA[ww * 256 + tid], sca, ov);
            }
            reinterpret_cast<__nv_bfloat16*>(smem + SM_Q)[tid] = __float2bfloat16_rn(__fdiv_rn(ov, L));
            {
                const int ip = 2 * NPAIR + warp + 8 - NS;
                if (ip >= 2 * NPAIR) mbar_wait(bar_full + 8 * (ip % NS), (ip / NS) & 1);
            }
            bar_cons();
        }
        {
            const unsigned short* os = reinterpret_cast<const unsigned short*>(smem + SM_Q);
            uint32_t ob[4] = {0, 0, 0, 0};
            if (holder) {
                const int sh = odd ? 16 : 0;
                ob[0] = (uint32_t)os[warp * 16 + g] << sh;
                ob[1] = (uint32_t)os[warp * 16 + 8 + g] << sh;
                ob[2] = (uint32_t)os[128 + warp * 16 + g] << sh;
                ob[3] = (uint32_t)os[128 + warp * 16 + 8 + g] << sh;
            }
            const int i0 = 2 * NPAIR + warp, i1 = i0 + 8;
            const int s0 = i0 % NS, s1 = i1 % NS;
            const uint32_t t0 = sb + SM_RING + s0 * STAGE, t1 = sb + SM_RING + s1 * STAGE;
            uint32_t woff[4];
#pragma unroll
            for (int j = 0; j < 4; j++) woff[j] = ((lm >> 1) * 8 + lr) * 896 + (((2 * j + (lm & 1)) ^ lr) << 4);
            float acc[7][4][4];
            mbar_wait(bar_full + 8 * s0, (i0 / NS) & 1);
#pragma unroll
            for (int cg = 0; cg < 7; cg++)
#pragma unroll
                for (int j = 0; j < 4; j++) {
                    uint32_t a[4];
                    acc[cg][j][0] = acc[cg][j][1] = acc[cg][j][2] = acc[cg][j][3] = 0.f;
                    ldsm4t(a, t0 + woff[j] + cg * 128);
                    mma16816(acc[cg][j], a, ob[0], ob[1]);
                }
            __syncwarp();
            if (lane == 0) mbar_arrive(bar_empty + 8 * s0);
            mbar_wait(bar_full + 8 * s1, (i1 / NS) & 1);
#pragma unroll
            for (int cg = 0; cg < 7; cg++) {
#pragma unroll
                for (int j = 0; j < 4; j++) {
                    uint32_t a[4];
                    ldsm4t(a, t1 + woff[j] + cg * 128);
                    mma16816(acc[cg][j], a, ob[2], ob[3]);
                }
            }
#pragma unroll
            for (int cg = 0; cg < 7; cg++) {
                float e[4], f[4];
#pragma unroll
                for (int j = 0; j < 4; j++) { e[j] = acc[cg][j][0] + acc[cg][j][3]; f[j] = acc[cg][j][1] + acc[cg][j][2]; }
                e[0] += __shfl_xor_sync(0xffffffffu, e[1], 1); f[0] += __shfl_xor_sync(0xffffffffu, f[1], 1);
                e[2] += __shfl_xor_sync(0xffffffffu, e[3], 1); f[2] += __shfl_xor_sync(0xffffffffu, f[3], 1);
                e[0] += __shfl_xor_sync(0xffffffffu, e[2], 2); f[0] += __shfl_xor_sync(0xffffffffu, f[2], 2);
                sA[warp * D_ + cg * 64 + t * 16 + g] = e[0];
                sA[warp * D_ + cg * 64 + t * 16 + 8 + g] = f[0];
            }
            bar_cons();
            if (tid < 112) {
                float4 a = *reinterpret_cast<const float4*>(sA + tid * 4);
#pragma unroll
                for (int ww = 1; ww < 8; ww++) {
                    const float4 v = *reinterpret_cast<const float4*>(sA + ww * D_ + tid * 4);
                    a.x += v.x; a.y += v.y; a.z += v.z; a.w += v.w;
                }
                st_relaxed4(&g_part[(b * NSRC + h) * D_ + tid * 4],
                            make_uint4(enc_f32(a.x), enc_f32(a.y), enc_f32(a.z), enc_f32(a.w)));
            }
        }
    } else {
        const int f = cta - NATT;
        if (warp == NCW) {
            int s = 0; uint32_t ph = 1;
            for (int j = 0; j < 56; j++) {
                mbar_wait(bar_empty + 8 * s, ph);
                if (lane == 0) mbar_expect_tx(bar_full + 8 * s, WO_TILE);
                __syncwarp();
                if (lane < 16) {
                    const char* src = (j < 28)
                        ? reinterpret_cast<const char*>(w1) + ((size_t)(j * 16 + lane) * F_ + f * D_) * 2
                        : reinterpret_cast<const char*>(w2) + ((size_t)(f * D_ + (j - 28) * 16 + lane) * D_) * 2;
                    bulk_load(sb + SM_RING + s * STAGE + lane * FP, src, 896, bar_full + 8 * s);
                }
                if (++s == NS) { s = 0; ph ^= 1; }
            }
            return;
        }
        unsigned char* xs = smem + SM_A;
        unsigned char* hs = smem + SM_A + 8 * FP;
        {
            float xn[14];
            layernorm_row(x, warp, lane, xn);
#pragma unroll
            for (int i = 0; i < 7; i++)
                *reinterpret_cast<uint32_t*>(xs + warp * FP + (lane + 32 * i) * 4) = bf16bits(xn[2 * i]) | (bf16bits(xn[2 * i + 1]) << 16);
        }
        bar_cons();
        const uint32_t aoff = ((lm >> 1) * 8 + lr) * FP + (lm & 1) * 16 + warp * 128;
        int s = 0; uint32_t ph = 0;
#pragma unroll 1
        for (int pass = 0; pass < 2; pass++) {
            float acc[4][4];
#pragma unroll
            for (int j = 0; j < 4; j++) acc[j][0] = acc[j][1] = acc[j][2] = acc[j][3] = 0.f;
            if (warp < 7) {
                const unsigned char* as = (pass == 0 ? xs : hs) + g * FP + t * 4;
                for (int kt = 0; kt < 28; kt++) {
                    const uint32_t b0 = *reinterpret_cast<const uint32_t*>(as + kt * 32);
                    const uint32_t b1 = *reinterpret_cast<const uint32_t*>(as + kt * 32 + 16);
                    mbar_wait(bar_full + 8 * s, ph);
#pragma unroll
                    for (int j = 0; j < 4; j++) {
                        uint32_t a[4];
                        ldsm4t(a, sb + SM_RING + s * STAGE + aoff + j * 32);
                        mma16816(acc[j], a, b0, b1);
                    }
                    __syncwarp();
                    if (lane == 0) mbar_arrive(bar_empty + 8 * s);
                    if (++s == NS) { s = 0; ph ^= 1; }
                }
#pragma unroll
                for (int j = 0; j < 4; j++)
#pragma unroll
                    for (int e = 0; e < 4; e++) {
                        const int n = warp * 64 + j * 16 + (e >> 1) * 8 + g;
                        const int bb = 2 * t + (e & 1);
                        if (pass == 0) {
                            const float hv = bf16r(acc[j][e]);
                            const float sv = __fdiv_rn(hv, 1.0f + __expf(-hv));
                            *reinterpret_cast<__nv_bfloat16*>(hs + bb * FP + n * 2) = __float2bfloat16_rn(sv);
                        } else {
                            st_relaxed(&g_part[(bb * NSRC + 16 + f) * D_ + n], enc_f32(acc[j][e]));
                        }
                    }
            }
            bar_cons();
        }
        if (tid < 224) {
            const int bb = 2 * f + (tid >= 112 ? 1 : 0);
            const int c4 = (tid >= 112 ? tid - 112 : tid) * 4;
            uint32_t* src = &g_part[bb * NSRC * D_ + c4];
            const uint4 zero = make_uint4(0, 0, 0, 0);
            float y[4] = {0.f, 0.f, 0.f, 0.f};
#pragma unroll 1
            for (int k = 0; k < NFFN; k++) {
                uint4 v = ld_relaxed4(src + (16 + k) * D_);
                int it = 0;
                while (!all_set(v)) {
                    __nanosleep(200);
                    v = ld_relaxed4(src + (16 + k) * D_);
                    if (++it > (1 << 22)) __trap();
                }
                st_relaxed4(src + (16 + k) * D_, zero);
                y[0] += dec_f32(v.x); y[1] += dec_f32(v.y); y[2] += dec_f32(v.z); y[3] += dec_f32(v.w);
            }
            const uint2 xw = __ldg(reinterpret_cast<const uint2*>(x + bb * D_ + c4));
            {
                int it = 0;
                uint4 v0 = ld_relaxed4(src);
                while (!all_set(v0)) {
                    __nanosleep(100);
                    v0 = ld_relaxed4(src);
                    if (++it > (1 << 22)) __trap();
                }
            }
            uint4 v[16];
#pragma unroll
            for (int k = 0; k < 16; k++) v[k] = ld_relaxed4(src + k * D_);
            int it = 0;
            while (true) {
                bool ok = true;
#pragma unroll
                for (int k = 0; k < 16; k++) {
                    if (!all_set(v[k])) { ok = false; v[k] = ld_relaxed4(src + k * D_); }
                }
                if (ok) break;
                if (++it > (1 << 22)) __trap();
            }
            float a[4] = {0.f, 0.f, 0.f, 0.f};
#pragma unroll
            for (int k = 0; k < 16; k++) {
                a[0] += dec_f32(v[k].x); a[1] += dec_f32(v[k].y); a[2] += dec_f32(v[k].z); a[3] += dec_f32(v[k].w);
            }
            const float xv[4] = {bflo(xw.x), bfhi(xw.x), bflo(xw.y), bfhi(xw.y)};
            uint32_t r[4];
#pragma unroll
            for (int e = 0; e < 4; e++) r[e] = bf16bits(bf16r(xv[e] + bf16r(a[e])) + bf16r(y[e]));
            *reinterpret_cast<uint2*>(out + bb * D_ + c4) = make_uint2(r[0] | (r[1] << 16), r[2] | (r[3] << 16));
#pragma unroll
            for (int k = 0; k < 16; k++) st_relaxed4(src + k * D_, zero);
        }
    }
}

}

extern "C" void kernel_launch(void* const* d_in, const int* in_sizes, int n_in, void* d_out, int out_size) {
    (void)in_sizes; (void)n_in; (void)out_size;
    static bool attr_set = false;
    if (!attr_set) {
        cudaFuncSetAttribute(fused_decode_kernel, cudaFuncAttributeMaxDynamicSharedMemorySize, SMEM_BYTES);
        attr_set = true;
    }
    fused_decode_kernel<<<NATT + NFFN, NTHREADS, SMEM_BYTES>>>(
        (const __nv_bfloat16*)d_in[0], (const __nv_bfloat16*)d_in[1], (const __nv_bfloat16*)d_in[2],
        (const __nv_bfloat16*)d_in[3], (const __nv_bfloat16*)d_in[4], (const __nv_bfloat16*)d_in[6],
        (const __nv_bfloat16*)d_in[7], (__nv_bfloat16*)d_out);
}
```

```cpp
#include <cuda_runtime.h>
#include <cuda_bf16.h>
#include <stdint.h>

namespace {

constexpr int D_ = 448, DH = 256, F_ = 1792;
constexpr int NATT = 128, NFFN = 4;
constexpr int NTHREADS = 352;
constexpr int STAGE = 16384;
constexpr int NS = 12;
constexpr int NITEM = 256;
constexpr int NWIN = 112;
constexpr int W_TILE = 16 * 896;
constexpr int NSRC = 16 + NFFN;
constexpr int FP = 912;
constexpr int R_ = 4;
constexpr int OP = 288;
constexpr int MBW = 512;
constexpr int ST = R_ * OP + MBW;
constexpr int OSP = 576;
constexpr int THR_W = 16 * 32;
constexpr float THR_COMP = 1.5f;
constexpr int INF = 6;
constexpr int TOPN = 2;
constexpr int INF0 = 3;
constexpr int NFREE = 10;
constexpr int WO_AT = 253;
constexpr int OFF_L = 256, OFF_M = 264, OFF_CV = 265, OFF_CK = 272, OFF_MB = R_ * OP;

constexpr int SM_RING = 0;
constexpr int SM_A = NS * STAGE;
constexpr int SM_SC = SM_A + 14592;
constexpr int SM_QB = SM_SC + 8192;
constexpr int SM_MS = SM_QB + 2048;
constexpr int SM_MISC = SM_MS + 512;
constexpr int SM_BAR = SM_MISC + 16;
constexpr int SMEM_BYTES = SM_BAR + (2 * NS + 27) * 8;

__device__ __align__(128) uint32_t g_qv[NATT * 256];
__device__ __align__(128) uint32_t g_st[NATT * ST];
__device__ __align__(128) uint32_t g_part[8 * NSRC * D_];
__device__ __align__(128) uint32_t g_sync[32];

constexpr int SPIN_LIMIT = 1 << 22;

__device__ __forceinline__ uint32_t smem_u32(const void* p) { return (uint32_t)__cvta_generic_to_shared(p); }
__device__ __forceinline__ void mbar_init(uint32_t bar, int cnt) {
    asm volatile("mbarrier.init.shared::cta.b64 [%0], %1;" ::"r"(bar), "r"(cnt) : "memory");
}
__device__ __forceinline__ void mbar_expect_tx(uint32_t bar, uint32_t bytes) {
    asm volatile("mbarrier.arrive.expect_tx.shared::cta.b64 _, [%0], %1;" ::"r"(bar), "r"(bytes) : "memory");
}
__device__ __forceinline__ void mbar_arrive(uint32_t bar) {
    asm volatile("mbarrier.arrive.shared::cta.b64 _, [%0];" ::"r"(bar) : "memory");
}
__device__ __forceinline__ bool mbar_try_wait(uint32_t bar, uint32_t parity) {
    uint32_t ok;
    asm volatile(
        "{\n.reg .pred p;\nmbarrier.try_wait.parity.shared::cta.b64 p, [%1], %2;\nselp.u32 %0, 1, 0, p;\n}"
        : "=r"(ok) : "r"(bar), "r"(parity) : "memory");
    return ok;
}
__device__ __forceinline__ bool mbar_test_wait(uint32_t bar, uint32_t parity) {
    uint32_t ok;
    asm volatile(
        "{\n.reg .pred p;\nmbarrier.test_wait.parity.shared::cta.b64 p, [%1], %2;\nselp.u32 %0, 1, 0, p;\n}"
        : "=r"(ok) : "r"(bar), "r"(parity) : "memory");
    return ok;
}
__device__ __forceinline__ void mbar_wait(uint32_t bar, uint32_t parity) {
    int it = 0;
    while (!mbar_try_wait(bar, parity)) {
        if (++it > SPIN_LIMIT) __trap();
    }
}
__device__ __forceinline__ void bulk_load(uint32_t dst, const void* src, uint32_t bytes, uint32_t bar) {
    asm volatile("cp.async.bulk.shared::cluster.global.mbarrier::complete_tx::bytes [%0], [%1], %2, [%3];"
                 ::"r"(dst), "l"(src), "r"(bytes), "r"(bar) : "memory");
}
__device__ __forceinline__ void bulk_load_hint(uint32_t dst, const void* src, uint32_t bytes, uint32_t bar, uint64_t pol) {
    asm volatile("cp.async.bulk.shared::cluster.global.mbarrier::complete_tx::bytes.L2::cache_hint [%0], [%1], %2, [%3], %4;"
                 ::"r"(dst), "l"(src), "r"(bytes), "r"(bar), "l"(pol) : "memory");
}
__device__ __forceinline__ void cp_async16(uint32_t dst, const void* src) {
    asm volatile("cp.async.cg.shared.global [%0], [%1], 16;" ::"r"(dst), "l"(src) : "memory");
}
__device__ __forceinline__ void ldsm4(uint32_t (&r)[4], uint32_t addr) {
    asm volatile("ldmatrix.sync.aligned.m8n8.x4.shared.b16 {%0,%1,%2,%3}, [%4];"
                 : "=r"(r[0]), "=r"(r[1]), "=r"(r[2]), "=r"(r[3]) : "r"(addr) : "memory");
}
__device__ __forceinline__ void ldsm4t(uint32_t (&r)[4], uint32_t addr) {
    asm volatile("ldmatrix.sync.aligned.m8n8.x4.trans.shared.b16 {%0,%1,%2,%3}, [%4];"
                 : "=r"(r[0]), "=r"(r[1]), "=r"(r[2]), "=r"(r[3]) : "r"(addr) : "memory");
}
__device__ __forceinline__ void mma16816(float (&c)[4], const uint32_t (&a)[4], uint32_t b0, uint32_t b1) {
    asm volatile(
        "mma.sync.aligned.m16n8k16.row.col.f32.bf16.bf16.f32 {%0,%1,%2,%3}, {%4,%5,%6,%7}, {%8,%9}, {%0,%1,%2,%3};"
        : "+f"(c[0]), "+f"(c[1]), "+f"(c[2]), "+f"(c[3])
        : "r"(a[0]), "r"(a[1]), "r"(a[2]), "r"(a[3]), "r"(b0), "r"(b1));
}
__device__ __forceinline__ void bar_init_sync() { asm volatile("bar.sync 0, 352;" ::: "memory"); }
__device__ __forceinline__ void bar_init_arrive() { asm volatile("bar.arrive 0, 352;" ::: "memory"); }
__device__ __forceinline__ void bar_cons() { asm volatile("bar.sync 1, 256;" ::: "memory"); }
__device__ __forceinline__ void bar_o_sync() { asm volatile("bar.sync 2, 256;" ::: "memory"); }
__device__ __forceinline__ void bar_o_arrive() { asm volatile("bar.arrive 2, 256;" ::: "memory"); }
__device__ __forceinline__ void bar_main() { asm volatile("bar.sync 3, 128;" ::: "memory"); }

__device__ __forceinline__ uint32_t* ctl(int region, int off) { return g_st + region * ST + off; }
__device__ __forceinline__ int item_region(int i, int c) { return (i < NWIN) ? i : NWIN + (c >> 3); }
__device__ __forceinline__ uint32_t item_chunk(int i, int c) {
    return (uint32_t)((i < NWIN) ? i * 128 + c : NWIN * 128 + c * 16 + (i - NWIN));
}
__device__ __forceinline__ int ofrag(int ks, int r) { return ((r & 7) >> 1) * 144 + ks * 8 + (r >> 3) * 4 + (r & 1) * 2; }

__device__ __forceinline__ float bf16r(float x) { return __bfloat162float(__float2bfloat16_rn(x)); }
__device__ __forceinline__ uint32_t bf16bits(float x) { return (uint32_t)__bfloat16_as_ushort(__float2bfloat16_rn(x)); }
__device__ __forceinline__ float bflo(uint32_t w) { return __uint_as_float(w << 16); }
__device__ __forceinline__ float bfhi(uint32_t w) { return __uint_as_float(w & 0xffff0000u); }
__device__ __forceinline__ float ex2(float x) { float y; asm("ex2.approx.ftz.f32 %0, %1;" : "=f"(y) : "f"(x)); return y; }

__device__ __forceinline__ uint32_t ld_relaxed(const uint32_t* p) {
    uint32_t v; asm volatile("ld.relaxed.gpu.global.u32 %0, [%1];" : "=r"(v) : "l"(p) : "memory"); return v;
}
__device__ __forceinline__ uint32_t ld_acquire(const uint32_t* p) {
    uint32_t v; asm volatile("ld.acquire.gpu.global.u32 %0, [%1];" : "=r"(v) : "l"(p) : "memory"); return v;
}
__device__ __forceinline__ uint4 ld_relaxed4(const void* p) {
    uint4 v;
    asm volatile("ld.relaxed.gpu.global.v4.u32 {%0,%1,%2,%3}, [%4];" : "=r"(v.x), "=r"(v.y), "=r"(v.z), "=r"(v.w) : "l"(p) : "memory");
    return v;
}
__device__ __forceinline__ void st_relaxed(uint32_t* p, uint32_t v) {
    asm volatile("st.relaxed.gpu.global.u32 [%0], %1;" ::"l"(p), "r"(v) : "memory");
}
__device__ __forceinline__ void st_relaxed4(uint32_t* p, uint4 v) {
    asm volatile("st.relaxed.gpu.global.v4.u32 [%0], {%1,%2,%3,%4};" ::"l"(p), "r"(v.x), "r"(v.y), "r"(v.z), "r"(v.w) : "memory");
}
__device__ __forceinline__ void red_add_u32_if(int pred, uint32_t* p, uint32_t v) {
    asm volatile("{\n.reg .pred p;\nsetp.ne.s32 p, %2, 0;\n@p red.relaxed.gpu.global.add.u32 [%0], %1;\n}" ::"l"(p), "r"(v), "r"(pred) : "memory");
}
__device__ __forceinline__ void red_release_add_u32(uint32_t* p, uint32_t v) {
    asm volatile("red.release.gpu.global.add.u32 [%0], %1;" ::"l"(p), "r"(v) : "memory");
}
__device__ __forceinline__ void red_max_u32(uint32_t* p, uint32_t v) {
    asm volatile("red.relaxed.gpu.global.max.u32 [%0], %1;" ::"l"(p), "r"(v) : "memory");
}
__device__ __forceinline__ void red_add_f32(uint32_t* p, float v) {
    asm volatile("red.relaxed.gpu.global.add.f32 [%0], %1;" ::"l"(p), "f"(v) : "memory");
}
__device__ __forceinline__ void red_add_v4(uint32_t* p, float a, float b, float c, float d) {
    asm volatile("red.relaxed.gpu.global.add.v4.f32 [%0], {%1,%2,%3,%4};" ::"l"(p), "f"(a), "f"(b), "f"(c), "f"(d) : "memory");
}
__device__ __forceinline__ void ld_relaxed_if(uint32_t pred, uint32_t& v, const uint32_t* p) {
    asm volatile("{\n.reg .pred p;\nsetp.ne.u32 p, %2, 0;\n@p ld.relaxed.gpu.global.u32 %0, [%1];\n}" : "+r"(v) : "l"(p), "r"(pred) : "memory");
}
__device__ __forceinline__ void ld_relaxed4_if(uint32_t pred, uint4& v, const uint32_t* p) {
    asm volatile("{\n.reg .pred p;\nsetp.ne.u32 p, %5, 0;\n@p ld.relaxed.gpu.global.v4.u32 {%0,%1,%2,%3}, [%4];\n}"
                 : "+r"(v.x), "+r"(v.y), "+r"(v.z), "+r"(v.w) : "l"(p), "r"(pred) : "memory");
}
__device__ __forceinline__ void st_relaxed_if(int pred, uint32_t* p, uint32_t v) {
    asm volatile("{\n.reg .pred p;\nsetp.ne.s32 p, %2, 0;\n@p st.relaxed.gpu.global.u32 [%0], %1;\n}" ::"l"(p), "r"(v), "r"(pred) : "memory");
}
__device__ __forceinline__ void st_relaxed4_if(int pred, uint32_t* p, uint4 v) {
    asm volatile("{\n.reg .pred p;\nsetp.ne.s32 p, %5, 0;\n@p st.relaxed.gpu.global.v4.u32 [%0], {%1,%2,%3,%4};\n}"
                 ::"l"(p), "r"(v.x), "r"(v.y), "r"(v.z), "r"(v.w), "r"(pred) : "memory");
}
__device__ __forceinline__ void st_u16_if(int pred, void* p, uint32_t a) {
    asm volatile("{\n.reg .pred p;\nsetp.ne.s32 p, %2, 0;\n@p st.global.u16 [%0], %1;\n}" ::"l"(p), "h"((unsigned short)a), "r"(pred) : "memory");
}
__device__ __forceinline__ uint32_t enc_f32(float v) { return __float_as_uint(v + 0.0f) ^ 0x80000000u; }
__device__ __forceinline__ float dec_f32(uint32_t w) { return __uint_as_float(w ^ 0x80000000u); }
__device__ __forceinline__ bool all_set(const uint4& v) { return v.x != 0u && v.y != 0u && v.z != 0u && v.w != 0u; }
__device__ __forceinline__ uint32_t fkey(float f) { uint32_t b = __float_as_uint(f); return b ^ ((b >> 31) ? 0xffffffffu : 0x80000000u); }
__device__ __forceinline__ float funkey(uint32_t k) { return __uint_as_float(k ^ ((k >> 31) ? 0x80000000u : 0xffffffffu)); }

__device__ __forceinline__ void reduce_frag(const float (&o)[4][4], float& e, float& f) {
    float e0 = o[0][0] + o[0][3], f0 = o[0][1] + o[0][2];
    const float e1 = o[1][0] + o[1][3], f1 = o[1][1] + o[1][2];
    float e2 = o[2][0] + o[2][3], f2 = o[2][1] + o[2][2];
    const float e3 = o[3][0] + o[3][3], f3 = o[3][1] + o[3][2];
    e0 += __shfl_xor_sync(0xffffffffu, e1, 1); f0 += __shfl_xor_sync(0xffffffffu, f1, 1);
    e2 += __shfl_xor_sync(0xffffffffu, e3, 1); f2 += __shfl_xor_sync(0xffffffffu, f3, 1);
    e = e0 + __shfl_xor_sync(0xffffffffu, e2, 2);
    f = f0 + __shfl_xor_sync(0xffffffffu, f2, 2);
}

__device__ __forceinline__ float probs(uint2 sw, float m, int sh, uint32_t (&pb)[4]) {
    constexpr float SCL = 1.4426950408889634f * 0.0625f;
    const float p0 = ex2((bflo(sw.x) - m) * SCL), p1 = ex2((bfhi(sw.x) - m) * SCL);
    const float p2 = ex2((bflo(sw.y) - m) * SCL), p3 = ex2((bfhi(sw.y) - m) * SCL);
    pb[0] = bf16bits(p0) << sh; pb[1] = bf16bits(p1) << sh;
    pb[2] = bf16bits(p2) << sh; pb[3] = bf16bits(p3) << sh;
    return (p0 + p1) + (p2 + p3);
}

__device__ __forceinline__ void layernorm_row(const uint32_t (&xw)[7], float (&xn)[14]) {
    float v[14];
#pragma unroll
    for (int i = 0; i < 7; i++) { v[2 * i] = bflo(xw[i]); v[2 * i + 1] = bfhi(xw[i]); }
    float s = 0.f;
#pragma unroll
    for (int i = 0; i < 14; i++) s += v[i];
#pragma unroll
    for (int o = 16; o > 0; o >>= 1) s += __shfl_xor_sync(0xffffffffu, s, o);
    const float mean = s * (1.0f / D_);
    float ss = 0.f;
#pragma unroll
    for (int i = 0; i < 14; i++) { float d = v[i] - mean; ss += d * d; }
#pragma unroll
    for (int o = 16; o > 0; o >>= 1) ss += __shfl_xor_sync(0xffffffffu, ss, o);
    const float mb = bf16r(mean);
    const float var = bf16r(ss * (1.0f / D_));
    const float den = bf16r(sqrtf(bf16r(var + 1e-5f)));
#pragma unroll
    for (int i = 0; i < 14; i++) xn[i] = bf16r(__fdiv_rn(bf16r(v[i] - mb), den));
}

__global__ void __launch_bounds__(NTHREADS, 1)
fused_decode_kernel(const __nv_bfloat16* __restrict__ x, const __nv_bfloat16* __restrict__ kc,
                    const __nv_bfloat16* __restrict__ vc, const __nv_bfloat16* __restrict__ wq,
                    const __nv_bfloat16* __restrict__ wo, const __nv_bfloat16* __restrict__ w1,
                    const __nv_bfloat16* __restrict__ w2, __nv_bfloat16* __restrict__ out) {
    extern __shared__ __align__(1024) unsigned char smem[];
    const uint32_t sb = smem_u32(smem);
    const int tid = threadIdx.x, warp = tid >> 5, lane = tid & 31;
    const int cta = blockIdx.x;
    const bool is_att = cta < NATT;
    const uint32_t bar_full = sb + SM_BAR, bar_empty = bar_full + NS * 8;
    const uint32_t bar_zero = bar_empty + NS * 8, bar_wo = bar_zero + 8, bar_pp = bar_wo + 8, bar_go = bar_pp + 8;
    const uint32_t bar_m = bar_go + 8, bar_kd = bar_m + 64, bar_vd = bar_kd + 64;
    volatile uint32_t* misc = reinterpret_cast<volatile uint32_t*>(smem + SM_MISC);

    if (__builtin_expect(tid == 256 && is_att, 1)) {
        uint64_t pol0;
        asm volatile("createpolicy.fractional.L2::evict_first.b64 %0, 1.0;" : "=l"(pol0));
        for (int i = 0; i < TOPN; i++) mbar_init(bar_full + 8 * i, 1);
        asm volatile("fence.mbarrier_init.release.cluster;" ::: "memory");
        for (int i = 0; i < TOPN; i++) {
            mbar_expect_tx(bar_full + 8 * i, STAGE);
            bulk_load_hint(sb + SM_RING + i * STAGE, reinterpret_cast<const char*>(kc) + (size_t)item_chunk(i, cta) * STAGE,
                           STAGE, bar_full + 8 * i, pol0);
        }
    }
    __syncwarp();

    const int g = lane >> 2, t = lane & 3;
    const int lr = lane & 7, lm = lane >> 3;
    const int h = cta >> 3, sl = cta & 7;

    if (warp == 8) {
        uint64_t pol;
        asm volatile("createpolicy.fractional.L2::evict_first.b64 %0, 1.0;" : "=l"(pol));
        if (lane == 0) {
            for (int i = is_att ? TOPN : 0; i < NS; i++) mbar_init(bar_full + 8 * i, 1);
            for (int i = 0; i < NS; i++) mbar_init(bar_empty + 8 * i, is_att ? 1 : 7);
            mbar_init(bar_zero, 1);
            mbar_init(bar_wo, 64);
            mbar_init(bar_pp, 1);
            mbar_init(bar_go, 1);
            for (int i = 0; i < 8; i++) { mbar_init(bar_m + 8 * i, 1); mbar_init(bar_kd + 8 * i, 4); }
            for (int i = 0; i < 7; i++) mbar_init(bar_vd + 8 * i, 4);
            for (int i = 0; i < 4; i++) misc[i] = 0;
            asm volatile("fence.mbarrier_init.release.cluster;" ::: "memory");
        }
        __syncwarp();
        bar_init_arrive();
        if (is_att) {
            if (lane == 0) {
                const char* kp = reinterpret_cast<const char*>(kc);
                const char* vp = reinterpret_cast<const char*>(vc);
                int issued = TOPN, landed = -1, pub = 0, si = TOPN, sd = NS - 1, it = 0, inf = INF0 + 1;
                uint32_t phi = 1, phd = 1;
                uint32_t* gprog = &g_sync[0];
                asm volatile("" : "+l"(gprog));
                bool go = false;
                static_assert(WO_AT >= 246 && NS == 12 && INF <= 8, "slot bookkeeping");
                while (landed < NITEM || !go) {
                    if (issued < NITEM && issued - landed < inf && (issued < NFREE || (uint32_t)(issued * NATT) <= misc[0] + THR_W) &&
                        mbar_test_wait(bar_empty + 8 * si, phi ^ (si >= NS - 2 ? 1u : 0u))) {
                        const char* src = ((issued < 128) ? kp : vp) + (size_t)item_chunk(issued & 127, cta) * STAGE;
                        mbar_expect_tx(bar_full + 8 * si, STAGE);
                        bulk_load_hint(sb + SM_RING + si * STAGE, src, STAGE, bar_full + 8 * si, pol);
                        if (++issued == NITEM) misc[1] = 1;
                        if (++si == NS) { si = 0; phi ^= 1; }
                        it = 0;
                    }
                    if (landed < issued && mbar_test_wait(bar_full + 8 * sd, phd)) {
                        landed++;
                        const int pubnow = landed > 0 && (((landed + cta) & 1) == 0 || landed == NITEM);
                        red_add_u32_if(pubnow, gprog, landed - pub);
                        if (pubnow) pub = landed;
                        inf = (landed + INF0 < NFREE) ? INF0 : INF;
                        if (++sd == NS) { sd = 0; phd ^= 1; }
                        it = 0;
                    }
                    if (!go && issued == NITEM && landed >= WO_AT &&
                        mbar_test_wait(bar_empty + 8 * 4, 0) && mbar_test_wait(bar_empty + 8 * 5, 0)) {
                        mbar_arrive(bar_go);
                        go = true;
                    }
                    if (++it > (SPIN_LIMIT << 4)) __trap();
                }
            }
        } else {
            const int f = cta - NATT;
            int s = 0; uint32_t ph = 1;
            for (int j = 0; j < 56; j++) {
                mbar_wait(bar_empty + 8 * s, ph);
                if (lane == 0) mbar_expect_tx(bar_full + 8 * s, W_TILE);
                __syncwarp();
                if (lane < 16) {
                    const char* src = (j < 28)
                        ? reinterpret_cast<const char*>(w1) + ((size_t)(j * 16 + lane) * F_ + f * D_) * 2
                        : reinterpret_cast<const char*>(w2) + ((size_t)(f * D_ + (j - 28) * 16 + lane) * D_) * 2;
                    bulk_load(sb + SM_RING + s * STAGE + lane * FP, src, 896, bar_full + 8 * s);
                }
                if (++s == NS) { s = 0; ph ^= 1; }
            }
        }
        return;
    }
    if (warp >= 9) {
        if (!is_att) { bar_init_sync(); return; }
        if (warp == 9) {
            bar_init_sync();
            if (lane == 0) {
                int it = 0;
                const int ts = (int)clock();
                while (misc[1] == 0) {
                    const int t0 = (int)clock();
                    const uint32_t rel = ld_relaxed(&g_sync[0]) & 32767u;
                    const int t1 = (int)clock();
                    misc[0] = rel + (uint32_t)(THR_COMP * (float)rel * __fdividef((float)(t1 - t0), (float)(t1 - ts)));
                    if (++it > SPIN_LIMIT) __trap();
                }
            }
        } else {
            const uint32_t r = ld_relaxed(&g_sync[1]);
            for (int i = lane; i < ST / 4; i += 32) st_relaxed4(ctl(cta, i * 4), make_uint4(0, 0, 0, 0));
            if (cta < 112) {
                const int fb = cta / 14;
#pragma unroll
                for (int i = 0; i < 4; i++)
                    st_relaxed4(&g_part[(fb * NSRC + i * 4 + lm) * D_ + (cta - fb * 14) * 32 + lr * 4], make_uint4(0, 0, 0, 0));
            }
            bar_init_sync();
            if (lane == 0) {
                misc[2] = 0x10000u | (((r >> 7) + 1u) & 0xffffu);
                red_release_add_u32(&g_sync[1], 1u);
                const uint32_t target = (r & ~127u) + 128u;
                int it = 0;
                while ((int)(ld_acquire(&g_sync[1]) - target) < 0) {
                    if (++it > SPIN_LIMIT) __trap();
                }
                mbar_arrive(bar_zero);
            }
        }
        __syncwarp();
        mbar_wait(bar_go, 0);
        if (lane < 28) {
            const int r0 = (warp - 9) * 128 + lane / 7, c = lane % 7;
            const char* wp = reinterpret_cast<const char*>(wo) + ((size_t)(h * DH + r0) * D_ + sl * 56) * 2 + c * 16;
            const uint32_t dp = sb + SM_RING + 4 * STAGE + r0 * 112 + c * 16;
#pragma unroll 8
            for (int i = 0; i < 32; i++) cp_async16(dp + i * 448, wp + i * 4 * 896);
        }
        asm volatile("cp.async.mbarrier.arrive.noinc.shared::cta.b64 [%0];" ::"r"(bar_wo) : "memory");
        asm volatile("cp.async.wait_all;" ::: "memory");
        return;
    }

    if (__builtin_expect(is_att, 1)) {
        uint32_t xw[7];
#pragma unroll
        for (int i = 0; i < 7; i++) xw[i] = __ldg(reinterpret_cast<const uint32_t*>(x + warp * D_) + lane + 32 * i);
        const uint32_t wqs = sb + SM_RING + (NS - 2) * STAGE;
        {
            const int r0 = tid >> 2, c = tid & 3;
            const __nv_bfloat16* wp = wq + (size_t)r0 * 4096 + 32 * cta + 8 * c;
            const uint32_t dp = wqs + r0 * 64 + ((c ^ ((r0 >> 1) & 3)) << 4);
#pragma unroll
            for (int i = 0; i < 7; i++) cp_async16(dp + i * 4096, wp + (size_t)i * 64 * 4096);
        }
        bar_init_sync();
        uint32_t tag;
        {
            unsigned char* xs = smem + SM_A;
            float* red = reinterpret_cast<float*>(smem + SM_A + 8 * FP);
            float xn[14];
            layernorm_row(xw, xn);
#pragma unroll
            for (int i = 0; i < 7; i++)
                *reinterpret_cast<uint32_t*>(xs + warp * FP + (lane + 32 * i) * 4) = bf16bits(xn[2 * i]) | (bf16bits(xn[2 * i + 1]) << 16);
            asm volatile("cp.async.wait_all;" ::: "memory");
            bar_cons();
            if (warp < 7) {
                float c0[4] = {0.f, 0.f, 0.f, 0.f}, c1[4] = {0.f, 0.f, 0.f, 0.f};
                const int row = warp * 64 + (lm >> 1) * 8 + lr;
                const uint32_t sw = (lr >> 1) & 3;
                const uint32_t a0 = wqs + row * 64 + ((((lm & 1)) ^ sw) << 4), a1 = wqs + row * 64 + ((((lm & 1) + 2) ^ sw) << 4);
                const unsigned char* bp = xs + g * FP + t * 4 + warp * 128;
#pragma unroll
                for (int ks = 0; ks < 4; ks++) {
                    uint32_t fa[4], fb[4];
                    ldsm4t(fa, a0 + ks * 1024);
                    ldsm4t(fb, a1 + ks * 1024);
                    const uint32_t b0 = *reinterpret_cast<const uint32_t*>(bp + ks * 32);
                    const uint32_t b1 = *reinterpret_cast<const uint32_t*>(bp + ks * 32 + 16);
                    mma16816(c0, fa, b0, b1);
                    mma16816(c1, fb, b0, b1);
                }
                float* rp = red + warp * 256 + 2 * t * 32 + g;
                rp[0] = c0[0]; rp[32] = c0[1]; rp[8] = c0[2]; rp[40] = c0[3];
                rp[16] = c1[0]; rp[48] = c1[1]; rp[24] = c1[2]; rp[56] = c1[3];
            }
            asm volatile("fence.proxy.async.shared::cta;" ::: "memory");
            bar_cons();
            if (tid == 0) { mbar_arrive(bar_empty + 8 * (NS - 2)); mbar_arrive(bar_empty + 8 * (NS - 1)); }
            float qv = 0.f;
#pragma unroll
            for (int ww = 0; ww < 7; ww++) qv += red[ww * 256 + tid];
            {
                int it = 0;
                while ((tag = misc[2]) == 0u) { if (++it > (SPIN_LIMIT << 4)) __trap(); }
                tag &= 0xffffu;
            }
            st_relaxed(&g_qv[(warp * 16 + h) * 256 + sl * 32 + lane], (bf16bits(qv) << 16) | tag);
        }

        if (warp < 4) {
            uint32_t koff[4], voff[4];
#pragma unroll
            for (int j = 0; j < 4; j++) {
                koff[j] = ((lm & 1) * 8 + lr) * 512 + (((2 * j + (lm >> 1)) ^ lr) << 4);
                voff[j] = ((lm >> 1) * 8 + lr) * 512 + (((2 * j + (lm & 1)) ^ lr) << 4);
            }
            const bool holder = (t == (g >> 1));
            const bool odd = g & 1;
            const int psh = odd ? 16 : 0;
            uint32_t* qs = reinterpret_cast<uint32_t*>(smem + SM_QB + warp * 512);
            uint2* scs = reinterpret_cast<uint2*>(smem + SM_SC);
            const float* ms = reinterpret_cast<const float*>(smem + SM_MS);
            float o[4][4];
            float lacc = 0.f;
#pragma unroll
            for (int c = 0; c < 4; c++) { o[c][0] = o[c][1] = o[c][2] = o[c][3] = 0.f; }
            int slot = warp; uint32_t ph = 0;
#pragma unroll 1
            for (int pass = 0; pass < 2; pass++) {
                int live = pass;
                asm volatile("" : "+r"(live));
                if (!live) {
                    uint32_t qf[32];
                    const uint32_t* qsrc = g_qv + warp * 256 + lane * 8;
                    uint4 qa = ld_relaxed4(qsrc), qb = ld_relaxed4(qsrc + 4);
#pragma unroll 1
                    for (int i = warp; i < 128; i += 4) {
                        if (i < NWIN + 4) {
                            int it = 0;
                            while (true) {
                                const uint32_t bad = ((qa.x ^ tag) | (qa.y ^ tag) | (qa.z ^ tag) | (qa.w ^ tag) |
                                                      (qb.x ^ tag) | (qb.y ^ tag) | (qb.z ^ tag) | (qb.w ^ tag)) & 0xffffu;
                                if (__all_sync(0xffffffffu, bad == 0u)) break;
                                qa = ld_relaxed4(qsrc); qb = ld_relaxed4(qsrc + 4);
                                if (++it > SPIN_LIMIT) __trap();
                            }
                            *reinterpret_cast<uint4*>(qs + lane * 4) =
                                make_uint4(__byte_perm(qa.x, qa.y, 0x7632), __byte_perm(qa.z, qa.w, 0x7632),
                                           __byte_perm(qb.x, qb.y, 0x7632), __byte_perm(qb.z, qb.w, 0x7632));
                            if (i < NWIN) {
                                qsrc = g_qv + item_region(i + 4, cta) * 256 + lane * 8;
                                qa = ld_relaxed4(qsrc); qb = ld_relaxed4(qsrc + 4);
                            }
                            __syncwarp();
#pragma unroll
                            for (int v = 0; v < 32; v++) qf[v] = qs[((v ^ g) << 2) + t];
                        }
                        const uint32_t kb = sb + SM_RING + slot * STAGE;
                        mbar_wait(bar_full + 8 * slot, ph);
                        float sc[4][4];
#pragma unroll
                        for (int c = 0; c < 4; c++) { sc[c][0] = sc[c][1] = sc[c][2] = sc[c][3] = 0.f; }
#pragma unroll
                        for (int c = 0; c < 16; c++) {
                            uint32_t a0[4], a1[4];
                            ldsm4(a0, kb + koff[c & 3] + (c >> 2) * 128);
                            ldsm4(a1, kb + koff[c & 3] + (c >> 2) * 128 + 8192);
                            mma16816(sc[c & 1], a0, qf[2 * c], qf[2 * c + 1]);
                            mma16816(sc[2 + (c & 1)], a1, qf[2 * c], qf[2 * c + 1]);
                        }
                        __syncwarp();
                        if (lane == 0) mbar_arrive(bar_empty + 8 * slot);
                        slot += 4; if (slot >= NS) { slot -= NS; ph ^= 1; }
                        const uint32_t s0 = bf16bits(odd ? sc[0][1] + sc[1][1] : sc[0][0] + sc[1][0]);
                        const uint32_t s1 = bf16bits(odd ? sc[0][3] + sc[1][3] : sc[0][2] + sc[1][2]);
                        const uint32_t s2 = bf16bits(odd ? sc[2][1] + sc[3][1] : sc[2][0] + sc[3][0]);
                        const uint32_t s3 = bf16bits(odd ? sc[2][3] + sc[3][3] : sc[2][2] + sc[3][2]);
                        uint32_t key = 0;
                        if (holder) {
                            scs[i * 8 + g] = make_uint2(s0 | (s1 << 16), s2 | (s3 << 16));
                            key = max(max(fkey(bflo(s0)), fkey(bflo(s1))), max(fkey(bflo(s2)), fkey(bflo(s3))));
                        }
                        key = __reduce_max_sync(0xffffffffu, key);
                        __syncwarp();
                        if (lane == 0) {
                            if (i < 4) mbar_wait(bar_zero, 0);
                            red_max_u32(ctl(item_region(i, cta), OFF_M), key);
                            if ((i & 15) >= 12) mbar_arrive(bar_kd + 8 * (i >> 4));
                        }
                    }
                } else {
                    uint32_t* accp = g_st + (cta % R_) * OP + lane * 4;
#pragma unroll 1
                    for (int i = warp; i < NWIN; i += 4) {
                        if ((i & 15) < 4) mbar_wait(bar_m + 8 * (i >> 4), 0);
                        uint32_t pb[4] = {0, 0, 0, 0};
                        float ls = 0.f;
                        if (holder) ls = probs(scs[i * 8 + g], ms[i], psh, pb);
#pragma unroll
                        for (int of = 16; of > 0; of >>= 1) ls += __shfl_xor_sync(0xffffffffu, ls, of);
                        const uint32_t vb = sb + SM_RING + slot * STAGE;
                        mbar_wait(bar_full + 8 * slot, ph);
                        float e[4], f[4];
#pragma unroll
                        for (int j = 0; j < 4; j++) {
                            float oo[4][4];
#pragma unroll
                            for (int c = 0; c < 4; c++) {
                                uint32_t a0[4], a1[4];
                                oo[c][0] = oo[c][1] = oo[c][2] = oo[c][3] = 0.f;
                                ldsm4t(a0, vb + voff[c] + j * 128);
                                ldsm4t(a1, vb + voff[c] + j * 128 + 8192);
                                mma16816(oo[c], a0, pb[0], pb[1]);
                                mma16816(oo[c], a1, pb[2], pb[3]);
                            }
                            reduce_frag(oo, e[j], f[j]);
                        }
                        __syncwarp();
                        if (lane == 0) mbar_arrive(bar_empty + 8 * slot);
                        slot += 4; if (slot >= NS) { slot -= NS; ph ^= 1; }
                        uint32_t* ap = accp + (size_t)i * ST;
                        red_add_v4(ap, e[0], f[0], e[1], f[1]);
                        red_add_v4(ap + 128, e[2], f[2], e[3], f[3]);
                        if (lane == 0) red_add_f32(ap + OFF_L, ls);
                        if ((i & 15) >= 12) {
                            __syncwarp();
                            if (lane == 0) mbar_arrive(bar_vd + 8 * (i >> 4));
                        }
                    }
                    mbar_wait(bar_m + 8 * 7, 0);
                    const float m7 = ms[NWIN + h];
                    static_assert((128 + NWIN) % NS == 0, "slot bookkeeping");
#pragma unroll 1
                    for (int i = NWIN; i < 128; i++) {
                        uint32_t pb[4] = {0, 0, 0, 0};
                        if (holder) lacc += probs(scs[i * 8 + g], m7, psh, pb);
                        if (i == 127) {
#pragma unroll
                            for (int of = 16; of > 0; of >>= 1) lacc += __shfl_xor_sync(0xffffffffu, lacc, of);
                        }
                        const int k = i - NWIN, sl7 = (k >= NS) ? k - NS : k;
                        const uint32_t vb = sb + SM_RING + sl7 * STAGE + warp * 128;
                        mbar_wait(bar_full + 8 * sl7, (((128 + NWIN) / NS) + (k >= NS ? 1 : 0)) & 1);
#pragma unroll
                        for (int c = 0; c < 4; c++) {
                            uint32_t a0[4], a1[4];
                            ldsm4t(a0, vb + voff[c]);
                            ldsm4t(a1, vb + voff[c] + 8192);
                            mma16816(o[c], a0, pb[0], pb[1]);
                            mma16816(o[c], a1, pb[2], pb[3]);
                        }
                        if (k < 6) {
                            bar_main();
                            if (tid == 0) mbar_arrive(bar_empty + 8 * sl7);
                        }
                    }
                }
                {
                    float e, f;
                    reduce_frag(o, e, f);
                    const uint32_t le = enc_f32(lacc);
                    st_relaxed4_if(live, ctl(cta, OFF_MB) + tid * 4, make_uint4(enc_f32(e), enc_f32(f), le, le));
                    if (tid == 0 && live) mbar_arrive(bar_pp);
                }
                {
                    const uint32_t abase = sb + SM_RING + 4 * STAGE + ((lm >> 1) * 8 + lr) * 112 + warp * 32 + (lm & 1) * 16;
                    if (live) mbar_wait(bar_wo, 0);
                    uint32_t a[16][4];
#pragma unroll
                    for (int ks = 0; ks < 16; ks++) ldsm4t(a[ks], abase + ks * 16 * 112);
                    bar_o_sync();
                    const uint4* bp = reinterpret_cast<const uint4*>(smem + SM_A + g * OSP + t * 144);
                    float c[4][4];
#pragma unroll
                    for (int j = 0; j < 4; j++) c[j][0] = c[j][1] = c[j][2] = c[j][3] = 0.f;
#pragma unroll
                    for (int k2 = 0; k2 < 8; k2++) {
                        const uint4 bv = bp[k2];
                        mma16816(c[(2 * k2) & 3], a[2 * k2], bv.x, bv.y);
                        mma16816(c[(2 * k2 + 1) & 3], a[2 * k2 + 1], bv.z, bv.w);
                    }
                    uint32_t* dst = &g_part[(2 * t * NSRC + h) * D_ + sl * 56 + warp * 16 + g];
                    st_relaxed_if(live, dst, enc_f32((c[0][0] + c[1][0]) + (c[2][0] + c[3][0])));
                    st_relaxed_if(live, dst + NSRC * D_, enc_f32((c[0][1] + c[1][1]) + (c[2][1] + c[3][1])));
                    st_relaxed_if(live && warp < 3, dst + 8, enc_f32((c[0][2] + c[1][2]) + (c[2][2] + c[3][2])));
                    st_relaxed_if(live && warp < 3, dst + NSRC * D_ + 8, enc_f32((c[0][3] + c[1][3]) + (c[2][3] + c[3][3])));
                }
            }
            return;
        }

        unsigned char* os = smem + SM_A;
#pragma unroll 1
        for (int pass = 0; pass < 2; pass++) {
            int live = pass;
            asm volatile("" : "+r"(live));
            if (live) mbar_wait(bar_zero, 0);
            if (warp == 4) {
                if (live) {
                    float* ms = reinterpret_cast<float*>(smem + SM_MS);
#pragma unroll 1
                    for (int bb = 0; bb <= 8; bb++) {
                        if (bb < 8 && lane == 0) {
                            mbar_wait(bar_kd + 8 * bb, 0);
                            red_release_add_u32(ctl(bb * 16, OFF_CK), 1u);
                        }
                        if (bb >= 1) {
                            const int bm = bb - 1;
                            if (lane == 0) {
                                int it = 0;
                                while (ld_acquire(ctl(bm * 16, OFF_CK)) < (uint32_t)NATT) {
                                    __nanosleep(200);
                                    if (++it > SPIN_LIMIT) __trap();
                                }
                            }
                            __syncwarp();
                            if (lane < 16) ms[bm * 16 + lane] = funkey(ld_relaxed(ctl(bm * 16 + lane, OFF_M)));
                            __syncwarp();
                            if (lane == 0) mbar_arrive(bar_m + 8 * bm);
                        }
                        __syncwarp();
                    }
                    if (lane == 0) {
#pragma unroll 1
                        for (int bb = 0; bb < 7; bb++) {
                            mbar_wait(bar_vd + 8 * bb, 0);
                            red_release_add_u32(ctl(bb * 16, OFF_CV), 1u);
                        }
                    }
                    __syncwarp();
                }
            } else if (live) {
#pragma unroll 1
                for (int bb = warp - 5; bb < 7; bb += 3) {
                    mbar_wait(bar_vd + 8 * bb, 0);
                    if (lane == 0) {
                        int it = 0;
                        while (ld_acquire(ctl(bb * 16, OFF_CV)) < (uint32_t)NATT) {
                            __nanosleep(200);
                            if (++it > SPIN_LIMIT) __trap();
                        }
                    }
                    __syncwarp();
                    const uint32_t* ap = ctl(bb * 16 + h, 0);
                    uint4 u0[R_], u1[R_]; uint32_t lw[R_];
#pragma unroll
                    for (int r = 0; r < R_; r++) {
                        u0[r] = ld_relaxed4(ap + r * OP + lane * 4);
                        u1[r] = ld_relaxed4(ap + r * OP + 128 + lane * 4);
                        lw[r] = ld_relaxed(ap + r * OP + OFF_L);
                    }
                    float a[8] = {0.f, 0.f, 0.f, 0.f, 0.f, 0.f, 0.f, 0.f}, l = 0.f;
#pragma unroll
                    for (int r = 0; r < R_; r++) {
                        a[0] += __uint_as_float(u0[r].x); a[1] += __uint_as_float(u0[r].y);
                        a[2] += __uint_as_float(u0[r].z); a[3] += __uint_as_float(u0[r].w);
                        a[4] += __uint_as_float(u1[r].x); a[5] += __uint_as_float(u1[r].y);
                        a[6] += __uint_as_float(u1[r].z); a[7] += __uint_as_float(u1[r].w);
                        l += __uint_as_float(lw[r]);
                    }
                    const float rl = __frcp_rn(l);
#pragma unroll
                    for (int k = 0; k < 8; k++)
                        *reinterpret_cast<__nv_bfloat16*>(os + bb * OSP + ofrag((k >> 1) * 4 + t, (k & 1) * 8 + g)) = __float2bfloat16_rn(a[k] * rl);
                }
            }
            {
                const int mt = warp - 4;
                const bool fin = cta < 112 && warp == 7;
                const int fb = cta / 14, col = (cta - fb * 14) * 32 + lane;
                uint32_t* src = &g_part[fb * NSRC * D_ + col];
                unsigned short xr = 0;
                uint32_t v[NSRC];
#pragma unroll
                for (int k = 0; k < NSRC; k++) v[k] = 1u;
                const uint32_t* mb = ctl(h * 8, OFF_MB) + (tid - 128) * 4;
                uint4 u[8];
#pragma unroll
                for (int r = 0; r < 8; r++) u[r] = make_uint4(1, 1, 1, 1);
                if (live) {
                    if (fin) {
                        asm volatile("ld.global.nc.u16 %0, [%1];" : "=h"(xr) : "l"(x + fb * D_ + col) : "memory");
                        int w = 0;
                        do {
#pragma unroll
                            for (int k = 16; k < NSRC; k++) v[k] = ld_relaxed(src + k * D_);
                            if (++w > SPIN_LIMIT) __trap();
                        } while (v[16] == 0u || v[17] == 0u || v[18] == 0u || v[19] == 0u);
#pragma unroll
                        for (int k = 16; k < NSRC; k++) st_relaxed(src + k * D_, 0u);
#pragma unroll
                        for (int k = 0; k < 16; k++) v[k] = 0u;
                        __syncwarp();
                    }
                    mbar_wait(bar_pp, 0);
                }
                uint32_t need = live ? 0xffu : 0u;
                int it = 0;
                while (true) {
#pragma unroll
                    for (int r = 0; r < 8; r++) ld_relaxed4_if(need & (1u << r), u[r], mb + r * ST);
                    uint32_t miss = 0;
#pragma unroll
                    for (int r = 0; r < 8; r++) miss |= all_set(u[r]) ? 0u : (1u << r);
                    need = __reduce_or_sync(0xffffffffu, miss);
                    if (need == 0u) break;
                    if (++it > SPIN_LIMIT) __trap();
                }
                float oe = 0.f, of = 0.f, l = 0.f;
#pragma unroll
                for (int r = 0; r < 8; r++) { oe += dec_f32(u[r].x); of += dec_f32(u[r].y); l += dec_f32(u[r].z); }
                const float rl = __frcp_rn(l);
                *reinterpret_cast<__nv_bfloat16*>(os + 7 * OSP + ofrag(mt * 4 + t, g)) = __float2bfloat16_rn(oe * rl);
                *reinterpret_cast<__nv_bfloat16*>(os + 7 * OSP + ofrag(mt * 4 + t, 8 + g)) = __float2bfloat16_rn(of * rl);
                bar_o_arrive();
                if (fin) {
                    const float y = bf16r((dec_f32(v[16]) + dec_f32(v[17])) + (dec_f32(v[18]) + dec_f32(v[19])));
                    it = 0;
                    while (true) {
                        uint32_t miss = 0;
#pragma unroll
                        for (int k = 0; k < 16; k++) miss |= (v[k] == 0u) ? (1u << k) : 0u;
                        need = __reduce_or_sync(0xffffffffu, miss);
                        if (need == 0u) break;
#pragma unroll
                        for (int k = 0; k < 16; k++) ld_relaxed_if(need & (1u << k), v[k], src + k * D_);
                        if (++it > SPIN_LIMIT) __trap();
                    }
                    float a[4];
#pragma unroll
                    for (int k = 0; k < 4; k++)
                        a[k] = (dec_f32(v[4 * k]) + dec_f32(v[4 * k + 1])) + (dec_f32(v[4 * k + 2]) + dec_f32(v[4 * k + 3]));
                    const uint32_t r = bf16bits(bf16r(bflo(xr) + bf16r((a[0] + a[1]) + (a[2] + a[3]))) + y);
                    st_u16_if(live, out + fb * D_ + col, r);
                }
            }
        }
    } else {
        const int f = cta - NATT;
        uint32_t xw[7];
#pragma unroll
        for (int i = 0; i < 7; i++) xw[i] = __ldg(reinterpret_cast<const uint32_t*>(x + warp * D_) + lane + 32 * i);
        bar_init_sync();
        unsigned char* xs = smem + SM_A;
        unsigned char* hs = smem + SM_A + 8 * FP;
        {
            float xn[14];
            layernorm_row(xw, xn);
#pragma unroll
            for (int i = 0; i < 7; i++)
                *reinterpret_cast<uint32_t*>(xs + warp * FP + (lane + 32 * i) * 4) = bf16bits(xn[2 * i]) | (bf16bits(xn[2 * i + 1]) << 16);
        }
        bar_cons();
        const uint32_t aoff = ((lm >> 1) * 8 + lr) * FP + (lm & 1) * 16 + warp * 128;
        int s = 0; uint32_t ph = 0;
#pragma unroll 1
        for (int pass = 0; pass < 2; pass++) {
            float acc[4][4];
#pragma unroll
            for (int j = 0; j < 4; j++) acc[j][0] = acc[j][1] = acc[j][2] = acc[j][3] = 0.f;
            if (warp < 7) {
                const unsigned char* as = (pass == 0 ? xs : hs) + g * FP + t * 4;
                for (int kt = 0; kt < 28; kt++) {
                    const uint32_t b0 = *reinterpret_cast<const uint32_t*>(as + kt * 32);
                    const uint32_t b1 = *reinterpret_cast<const uint32_t*>(as + kt * 32 + 16);
                    mbar_wait(bar_full + 8 * s, ph);
#pragma unroll
                    for (int j = 0; j < 4; j++) {
                        uint32_t a[4];
                        ldsm4t(a, sb + SM_RING + s * STAGE + aoff + j * 32);
                        mma16816(acc[j], a, b0, b1);
                    }
                    __syncwarp();
                    if (lane == 0) mbar_arrive(bar_empty + 8 * s);
                    if (++s == NS) { s = 0; ph ^= 1; }
                }
#pragma unroll
                for (int j = 0; j < 4; j++)
#pragma unroll
                    for (int e = 0; e < 4; e++) {
                        const int n = warp * 64 + j * 16 + (e >> 1) * 8 + g;
                        const int bb = 2 * t + (e & 1);
                        if (pass == 0) {
                            const float hv = bf16r(acc[j][e]);
                            const float sv = __fdiv_rn(hv, 1.0f + expf(-hv));
                            *reinterpret_cast<__nv_bfloat16*>(hs + bb * FP + n * 2) = __float2bfloat16_rn(sv);
                        } else {
                            st_relaxed(&g_part[(bb * NSRC + 16 + f) * D_ + n], enc_f32(acc[j][e]));
                        }
                    }
            }
            bar_cons();
        }
    }
}

}

extern "C" void kernel_launch(void* const* d_in, const int* in_sizes, int n_in, void* d_out, int out_size) {
    (void)in_sizes; (void)n_in; (void)out_size;
    static bool attr_set = false;
    if (!attr_set) {
        cudaFuncSetAttribute(fused_decode_kernel, cudaFuncAttributeMaxDynamicSharedMemorySize, SMEM_BYTES);
        attr_set = true;
    }
    fused_decode_kernel<<<NATT + NFFN, NTHREADS, SMEM_BYTES>>>(
        (const __nv_bfloat16*)d_in[0], (const __nv_bfloat16*)d_in[1], (const __nv_bfloat16*)d_in[2],
        (const __nv_bfloat16*)d_in[3], (const __nv_bfloat16*)d_in[4], (const __nv_bfloat16*)d_in[6],
        (const __nv_bfloat16*)d_in[7], (__nv_bfloat16*)d_out);
}
```
